```python
import torch

def _softmax(x, axis=-1):
    return torch.softmax(x, dim=axis)
def _gelu(x):
    return torch.nn.functional.gelu(x, approximate="tanh")
def _silu(x):
    return torch.nn.functional.silu(x)
def _sigmoid(x):
    return torch.sigmoid(x)
def _layernorm(x, axis=-1, eps=1e-5):
    m = x.mean(dim=axis, keepdim=True)
    v = x.var(dim=axis, keepdim=True, unbiased=False)
    return (x - m) / torch.sqrt(v + eps)
def _scatter_add(tgt, idx, src, axis=0):
    return tgt.clone().index_add_(axis, idx, src)
def _segment_sum(src, seg, n):
    out = torch.zeros((n,) + src.shape[1:], dtype=src.dtype)
    return out.index_add_(0, seg, src)
def _pad(x, pw):
    flat = tuple(v for pair in reversed(pw) for v in pair)
    return torch.nn.functional.pad(x, flat)

kernel_name = 'sequential_preLN__mha_block__mixer_s_mlp__prompt'

def setup_inputs():

    _w = (lambda a: (lambda t: t.to(torch.bfloat16) if t.is_floating_point() else t)(torch.as_tensor(a)))
    def _A_setup():
        B, S, D, H = 1, 2048, 576, 32
        return {
            "x": _w((lambda *s: torch.randn(*s, dtype=torch.bfloat16) * 0.05)(B, S, D)),
            "wqkv": _w((lambda *s: torch.randn(*s, dtype=torch.bfloat16) * 0.05)(D, 3 * D)),
            "wo": _w((lambda *s: torch.randn(*s, dtype=torch.bfloat16) * 0.05)(D, D)),
        }
    _A_in = _A_setup()

    def _B_setup():
        B, S, D, F = 1, 2048, 576, 4608
        return {
            "x":  _w((lambda *s: torch.randn(*s, dtype=torch.bfloat16) * 0.05)(B, S, D)),
            "w1": _w((lambda *s: torch.randn(*s, dtype=torch.bfloat16) * 3.2)(D, D) * (D ** -0.5)),
            "w2": _w((lambda *s: torch.randn(*s, dtype=torch.bfloat16) * 3.2)(D, D) * (D ** -0.5)),
            "w3": _w((lambda *s: torch.randn(*s, dtype=torch.bfloat16) * 3.2)(D, F) * (D ** -0.5)),
            "w4": _w((lambda *s: torch.randn(*s, dtype=torch.bfloat16) * 3.2)(F, D) * (F ** -0.5)),
        }
    _B_in = _B_setup()

    return {
        "A_x": _A_in["x"],
        "A_wqkv": _A_in["wqkv"],
        "A_wo": _A_in["wo"],
        "B_x": _B_in["x"],
        "B_w1": _B_in["w1"],
        "B_w2": _B_in["w2"],
        "B_w3": _B_in["w3"],
        "B_w4": _B_in["w4"],
    }

def reference(A_x, A_wqkv, A_wo, B_x, B_w1, B_w2, B_w3, B_w4):
    def _A_ref(x, wqkv, wo):
        B, S, D = x.shape
        H = 32
        Dh = D // H
        qkv = (lambda x, *d: x.permute(*d))((x @ wqkv).reshape(B, S, 3, H, Dh), 2, 0, 3, 1, 4)
        q, k, v = qkv[0], qkv[1], qkv[2]
        scores = torch.einsum("bhqd,bhkd->bhqk", q, k) * (Dh ** -0.5)
        p = _softmax(scores, axis=-1)
        o = torch.einsum("bhqk,bhkd->bhqd", p, v)
        return (lambda x, *d: x.permute(*d))(o, 0, 2, 1, 3).reshape(B, S, D) @ wo

    def _B_ref(x, w1, w2, w3, w4):
        B, S, D = x.shape
        h = _gelu(_layernorm(x, axis=-1) @ w1)
        c = D // 4
        g0 = _pad(h[:, :, 0*c:1*c], ((0, 0), (1, 0), (0, 0)))[:, :S, :]
        g1 = _pad(h[:, :, 1*c:2*c], ((0, 0), (0, 1), (0, 0)))[:, 1:, :]
        g2 = _pad(h[:, :, 2*c:3*c], ((0, 0), (2, 0), (0, 0)))[:, :S, :]
        g3 = _pad(h[:, :, 3*c:   ], ((0, 0), (0, 2), (0, 0)))[:, 2:, :]
        hs = torch.concatenate([g0, g1, g2, g3], axis=-1) @ w2
        x1 = x + hs
        h2 = _gelu(_layernorm(x1, axis=-1) @ w3) @ w4
        return x1 + h2

    x = A_x
    h = x + _A_ref(_layernorm(x, axis=-1), A_wqkv, A_wo)
    h2 = h + _B_ref(_layernorm(h, axis=-1), B_w1, B_w2, B_w3, B_w4)
    return h2
```

```cpp
#include <cuda_runtime.h>
#include <cuda_bf16.h>
#include <cuda.h>
#include <stdint.h>

typedef __nv_bfloat16 bf16;
#define DEVINL __device__ __forceinline__

constexpr int S_ = 2048, D_ = 576, F_ = 4608, NH = 32;
constexpr float LN_EPS = 1e-5f;

__device__ __align__(1024) unsigned char g_img[NH * 256 * (512 + 640)];
#define g_qimg g_img
#define g_kvimg (g_img + NH * 256 * 512)
__device__ __align__(1024) bf16 g_O[S_ * D_];
__device__ __align__(1024) unsigned char g_Uimg[S_ * D_ * 2];
__device__ __align__(1024) unsigned char g_Himg[(size_t)S_ * F_ * 2];

#define TSTAMP(k, i)
#define CSTAMP(k, i)
DEVINL uint32_t smem_u32(const void* p) { return (uint32_t)__cvta_generic_to_shared(p); }
DEVINL uint64_t mkdesc(uint32_t addr, uint32_t lbo, uint32_t sbo, uint32_t mode) {
  return (uint64_t)((addr & 0x3FFFF) >> 4) | ((uint64_t)(lbo >> 4) << 16) | ((uint64_t)(sbo >> 4) << 32) | ((uint64_t)mode << 62);
}
#define WG_FENCE() asm volatile("wgmma.fence.sync.aligned;" ::: "memory")
#define WG_COMMIT() asm volatile("wgmma.commit_group.sync.aligned;" ::: "memory")
#define WG_WAIT(n) asm volatile("wgmma.wait_group.sync.aligned %0;" ::"n"(n) : "memory")
#define FENCE_ASYNC() asm volatile("fence.proxy.async.shared::cta;" ::: "memory")
#define PDL_WAIT() asm volatile("griddepcontrol.wait;" ::: "memory")
#define PDL_LAUNCH() asm volatile("griddepcontrol.launch_dependents;" ::: "memory")
DEVINL void mbar_init(uint32_t b, int c) { asm volatile("mbarrier.init.shared::cta.b64 [%0], %1;" ::"r"(b), "r"(c) : "memory"); }
DEVINL void mbar_init_fence() { asm volatile("fence.mbarrier_init.release.cluster;" ::: "memory"); }
DEVINL void mbar_expect(uint32_t b, uint32_t bytes) { asm volatile("mbarrier.arrive.expect_tx.shared::cta.b64 _, [%0], %1;" ::"r"(b), "r"(bytes) : "memory"); }
DEVINL void mbar_arrive(uint32_t b) { asm volatile("mbarrier.arrive.shared::cta.b64 _, [%0];" ::"r"(b) : "memory"); }
DEVINL void mbar_arrive_cluster(uint32_t remote_b) { asm volatile("mbarrier.arrive.shared::cluster.b64 _, [%0];" ::"r"(remote_b) : "memory"); }
DEVINL bool mbar_try(uint32_t b, uint32_t ph) {
  uint32_t ok;
  asm volatile("{\n.reg .pred p;\nmbarrier.try_wait.parity.shared::cta.b64 p, [%1], %2;\nselp.u32 %0,1,0,p;\n}" : "=r"(ok) : "r"(b), "r"(ph) : "memory");
  return ok;
}
DEVINL bool mbar_test(uint32_t b, uint32_t ph) {
  uint32_t ok;
  asm volatile("{\n.reg .pred p;\nmbarrier.test_wait.parity.shared::cta.b64 p, [%1], %2;\nselp.u32 %0,1,0,p;\n}" : "=r"(ok) : "r"(b), "r"(ph) : "memory");
  return ok;
}
DEVINL void mbar_wait(uint32_t b, uint32_t ph) {
  if (mbar_try(b, ph)) return;
  int n = 0;
  while (!mbar_try(b, ph)) { if (++n > (1 << 22)) __trap(); }
}
DEVINL uint32_t mapa(uint32_t a, uint32_t rank) { uint32_t r; asm("mapa.shared::cluster.u32 %0, %1, %2;" : "=r"(r) : "r"(a), "r"(rank)); return r; }
DEVINL uint32_t cluster_rank() { uint32_t r; asm("mov.u32 %0, %%cluster_ctarank;" : "=r"(r)); return r; }
DEVINL void cluster_sync() { asm volatile("barrier.cluster.arrive.relaxed.aligned;\nbarrier.cluster.wait.aligned;" ::: "memory"); }
DEVINL void bulk_g2s(uint32_t dst, const void* src, uint32_t bytes, uint32_t bar) {
  asm volatile("cp.async.bulk.shared::cluster.global.mbarrier::complete_tx::bytes [%0], [%1], %2, [%3];" ::"r"(dst), "l"(src), "r"(bytes), "r"(bar) : "memory");
}
DEVINL void bulk_s2s(uint32_t dst_cl, uint32_t src, uint32_t bytes, uint32_t bar_cl) {
  asm volatile("cp.async.bulk.shared::cluster.shared::cta.mbarrier::complete_tx::bytes [%0], [%1], %2, [%3];" ::"r"(dst_cl), "r"(src), "r"(bytes), "r"(bar_cl) : "memory");
}
DEVINL void bulk_s2g(void* dst, uint32_t src, uint32_t bytes) {
  asm volatile("cp.async.bulk.global.shared::cta.bulk_group [%0], [%1], %2;" ::"l"(dst), "r"(src), "r"(bytes) : "memory");
}
DEVINL void bulk_commit() { asm volatile("cp.async.bulk.commit_group;" ::: "memory"); }
DEVINL void bulk_wait_read0() { asm volatile("cp.async.bulk.wait_group.read 0;" ::: "memory"); }
DEVINL void bulk_wait0() { asm volatile("cp.async.bulk.wait_group 0;" ::: "memory"); }
DEVINL void l2_prefetch(const void* p, uint32_t bytes) { asm volatile("cp.async.bulk.prefetch.L2.global [%0], %1;" ::"l"(p), "r"(bytes) : "memory"); }
DEVINL void tma3d(uint32_t dst, const CUtensorMap* m, int c0, int c1, int c2, uint32_t bar) {
  asm volatile("cp.async.bulk.tensor.3d.shared::cluster.global.mbarrier::complete_tx::bytes [%0], [%1, {%3,%4,%5}], [%2];"
               ::"r"(dst), "l"(m), "r"(bar), "r"(c0), "r"(c1), "r"(c2) : "memory");
}
DEVINL void tma3d_mc(uint32_t dst, const CUtensorMap* m, int c0, int c1, int c2, uint32_t bar, uint16_t mask) {
  asm volatile("cp.async.bulk.tensor.3d.shared::cluster.global.mbarrier::complete_tx::bytes.multicast::cluster [%0], [%1, {%3,%4,%5}], [%2], %6;"
               ::"r"(dst), "l"(m), "r"(bar), "r"(c0), "r"(c1), "r"(c2), "h"(mask) : "memory");
}
DEVINL void tmap_prefetch(const CUtensorMap* m) { asm volatile("prefetch.tensormap [%0];" ::"l"(m) : "memory"); }
DEVINL void named_sync(int id, int n) { asm volatile("bar.sync %0, %1;" ::"r"(id), "r"(n) : "memory"); }
DEVINL float ex2f(float x) { float r; asm("ex2.approx.ftz.f32 %0,%1;" : "=f"(r) : "f"(x)); return r; }
DEVINL uint32_t packbf(float lo, float hi) { uint32_t r; asm("cvt.rn.bf16x2.f32 %0,%1,%2;" : "=r"(r) : "f"(hi), "f"(lo)); return r; }
DEVINL float bf_lo(uint32_t v) { return __uint_as_float(v << 16); }
DEVINL float bf_hi(uint32_t v) { return __uint_as_float(v & 0xFFFF0000u); }
DEVINL void stsm4(uint32_t addr, uint32_t r0, uint32_t r1, uint32_t r2, uint32_t r3) {
  asm volatile("stmatrix.sync.aligned.m8n8.x4.shared.b16 [%0], {%1,%2,%3,%4};" ::"r"(addr), "r"(r0), "r"(r1), "r"(r2), "r"(r3) : "memory");
}
DEVINL float gelu_f(float x) {
  float u = x * x, t;
  float w = x * fmaf(u, 0.044715f * 0.7978845608028654f, 0.7978845608028654f);
  asm("tanh.approx.f32 %0,%1;" : "=f"(t) : "f"(w));
  float h = 0.5f * x;
  return fmaf(h, t, h);
}
template <int N> DEVINL void pin_f(float (&a)[N]) {
#pragma unroll
  for (int i = 0; i < N; i++) asm volatile("" : "+f"(a[i])::"memory");
}
template <int N> DEVINL void def_f(float (&a)[N]) {
#pragma unroll
  for (int i = 0; i < N; i++) asm volatile("" : "=f"(a[i])::"memory");
}
template <int N> DEVINL void pin_r(uint32_t (&a)[N]) {
#pragma unroll
  for (int i = 0; i < N; i++) asm volatile("" : "+r"(a[i])::"memory");
}

DEVINL void wgmma_ss_n224t(float (&d)[112], uint64_t da, uint64_t db, int acc) {
  asm volatile("{\n.reg .pred p;\nsetp.ne.b32 p, %114, 0;\n"
    "wgmma.mma_async.sync.aligned.m64n224k16.f32.bf16.bf16 {%0,%1,%2,%3,%4,%5,%6,%7,%8,%9,%10,%11,%12,%13,%14,%15,%16,%17,%18,%19,%20,%21,%22,%23,%24,%25,%26,%27,%28,%29,%30,%31,%32,%33,%34,%35,%36,%37,%38,%39,%40,%41,%42,%43,%44,%45,%46,%47,%48,%49,%50,%51,%52,%53,%54,%55,%56,%57,%58,%59,%60,%61,%62,%63,%64,%65,%66,%67,%68,%69,%70,%71,%72,%73,%74,%75,%76,%77,%78,%79,%80,%81,%82,%83,%84,%85,%86,%87,%88,%89,%90,%91,%92,%93,%94,%95,%96,%97,%98,%99,%100,%101,%102,%103,%104,%105,%106,%107,%108,%109,%110,%111}, %112, %113, p, 1, 1, 0, 1;\n}\n"
    : "+f"(d[0]),"+f"(d[1]),"+f"(d[2]),"+f"(d[3]),"+f"(d[4]),"+f"(d[5]),"+f"(d[6]),"+f"(d[7]),"+f"(d[8]),"+f"(d[9]),"+f"(d[10]),"+f"(d[11]),"+f"(d[12]),"+f"(d[13]),"+f"(d[14]),"+f"(d[15]),"+f"(d[16]),"+f"(d[17]),"+f"(d[18]),"+f"(d[19]),"+f"(d[20]),"+f"(d[21]),"+f"(d[22]),"+f"(d[23]),"+f"(d[24]),"+f"(d[25]),"+f"(d[26]),"+f"(d[27]),"+f"(d[28]),"+f"(d[29]),"+f"(d[30]),"+f"(d[31]),"+f"(d[32]),"+f"(d[33]),"+f"(d[34]),"+f"(d[35]),"+f"(d[36]),"+f"(d[37]),"+f"(d[38]),"+f"(d[39]),"+f"(d[40]),"+f"(d[41]),"+f"(d[42]),"+f"(d[43]),"+f"(d[44]),"+f"(d[45]),"+f"(d[46]),"+f"(d[47]),"+f"(d[48]),"+f"(d[49]),"+f"(d[50]),"+f"(d[51]),"+f"(d[52]),"+f"(d[53]),"+f"(d[54]),"+f"(d[55]),"+f"(d[56]),"+f"(d[57]),"+f"(d[58]),"+f"(d[59]),"+f"(d[60]),"+f"(d[61]),"+f"(d[62]),"+f"(d[63]),"+f"(d[64]),"+f"(d[65]),"+f"(d[66]),"+f"(d[67]),"+f"(d[68]),"+f"(d[69]),"+f"(d[70]),"+f"(d[71]),"+f"(d[72]),"+f"(d[73]),"+f"(d[74]),"+f"(d[75]),"+f"(d[76]),"+f"(d[77]),"+f"(d[78]),"+f"(d[79]),"+f"(d[80]),"+f"(d[81]),"+f"(d[82]),"+f"(d[83]),"+f"(d[84]),"+f"(d[85]),"+f"(d[86]),"+f"(d[87]),"+f"(d[88]),"+f"(d[89]),"+f"(d[90]),"+f"(d[91]),"+f"(d[92]),"+f"(d[93]),"+f"(d[94]),"+f"(d[95]),"+f"(d[96]),"+f"(d[97]),"+f"(d[98]),"+f"(d[99]),"+f"(d[100]),"+f"(d[101]),"+f"(d[102]),"+f"(d[103]),"+f"(d[104]),"+f"(d[105]),"+f"(d[106]),"+f"(d[107]),"+f"(d[108]),"+f"(d[109]),"+f"(d[110]),"+f"(d[111])
    : "l"(da), "l"(db), "r"(acc));
}
DEVINL void wgmma_ss_n128(float (&d)[64], uint64_t da, uint64_t db, int acc) {
  asm volatile("{\n.reg .pred p;\nsetp.ne.b32 p, %66, 0;\n"
    "wgmma.mma_async.sync.aligned.m64n128k16.f32.bf16.bf16 {%0,%1,%2,%3,%4,%5,%6,%7,%8,%9,%10,%11,%12,%13,%14,%15,%16,%17,%18,%19,%20,%21,%22,%23,%24,%25,%26,%27,%28,%29,%30,%31,%32,%33,%34,%35,%36,%37,%38,%39,%40,%41,%42,%43,%44,%45,%46,%47,%48,%49,%50,%51,%52,%53,%54,%55,%56,%57,%58,%59,%60,%61,%62,%63}, %64, %65, p, 1, 1, 0, 0;\n}\n"
    : "+f"(d[0]),"+f"(d[1]),"+f"(d[2]),"+f"(d[3]),"+f"(d[4]),"+f"(d[5]),"+f"(d[6]),"+f"(d[7]),"+f"(d[8]),"+f"(d[9]),"+f"(d[10]),"+f"(d[11]),"+f"(d[12]),"+f"(d[13]),"+f"(d[14]),"+f"(d[15]),"+f"(d[16]),"+f"(d[17]),"+f"(d[18]),"+f"(d[19]),"+f"(d[20]),"+f"(d[21]),"+f"(d[22]),"+f"(d[23]),"+f"(d[24]),"+f"(d[25]),"+f"(d[26]),"+f"(d[27]),"+f"(d[28]),"+f"(d[29]),"+f"(d[30]),"+f"(d[31]),"+f"(d[32]),"+f"(d[33]),"+f"(d[34]),"+f"(d[35]),"+f"(d[36]),"+f"(d[37]),"+f"(d[38]),"+f"(d[39]),"+f"(d[40]),"+f"(d[41]),"+f"(d[42]),"+f"(d[43]),"+f"(d[44]),"+f"(d[45]),"+f"(d[46]),"+f"(d[47]),"+f"(d[48]),"+f"(d[49]),"+f"(d[50]),"+f"(d[51]),"+f"(d[52]),"+f"(d[53]),"+f"(d[54]),"+f"(d[55]),"+f"(d[56]),"+f"(d[57]),"+f"(d[58]),"+f"(d[59]),"+f"(d[60]),"+f"(d[61]),"+f"(d[62]),"+f"(d[63])
    : "l"(da), "l"(db), "r"(acc));
}
DEVINL void wgmma_rs_n24t(float (&d)[12], uint32_t a0, uint32_t a1, uint32_t a2, uint32_t a3, uint64_t db, int acc) {
  asm volatile("{\n.reg .pred p;\nsetp.ne.b32 p, %17, 0;\n"
    "wgmma.mma_async.sync.aligned.m64n24k16.f32.bf16.bf16 {%0,%1,%2,%3,%4,%5,%6,%7,%8,%9,%10,%11}, {%12,%13,%14,%15}, %16, p, 1, 1, 1;\n}\n"
    : "+f"(d[0]),"+f"(d[1]),"+f"(d[2]),"+f"(d[3]),"+f"(d[4]),"+f"(d[5]),"+f"(d[6]),"+f"(d[7]),"+f"(d[8]),"+f"(d[9]),"+f"(d[10]),"+f"(d[11])
    : "r"(a0), "r"(a1), "r"(a2), "r"(a3), "l"(db), "r"(acc));
}
DEVINL void wgmma_ss_n96t(float (&d)[48], uint64_t da, uint64_t db, int acc) {
  asm volatile("{\n.reg .pred p;\nsetp.ne.b32 p, %50, 0;\n"
    "wgmma.mma_async.sync.aligned.m64n96k16.f32.bf16.bf16 {%0,%1,%2,%3,%4,%5,%6,%7,%8,%9,%10,%11,%12,%13,%14,%15,%16,%17,%18,%19,%20,%21,%22,%23,%24,%25,%26,%27,%28,%29,%30,%31,%32,%33,%34,%35,%36,%37,%38,%39,%40,%41,%42,%43,%44,%45,%46,%47}, %48, %49, p, 1, 1, 0, 1;\n}\n"
    : "+f"(d[0]),"+f"(d[1]),"+f"(d[2]),"+f"(d[3]),"+f"(d[4]),"+f"(d[5]),"+f"(d[6]),"+f"(d[7]),"+f"(d[8]),"+f"(d[9]),"+f"(d[10]),"+f"(d[11]),"+f"(d[12]),"+f"(d[13]),"+f"(d[14]),"+f"(d[15]),"+f"(d[16]),"+f"(d[17]),"+f"(d[18]),"+f"(d[19]),"+f"(d[20]),"+f"(d[21]),"+f"(d[22]),"+f"(d[23]),"+f"(d[24]),"+f"(d[25]),"+f"(d[26]),"+f"(d[27]),"+f"(d[28]),"+f"(d[29]),"+f"(d[30]),"+f"(d[31]),"+f"(d[32]),"+f"(d[33]),"+f"(d[34]),"+f"(d[35]),"+f"(d[36]),"+f"(d[37]),"+f"(d[38]),"+f"(d[39]),"+f"(d[40]),"+f"(d[41]),"+f"(d[42]),"+f"(d[43]),"+f"(d[44]),"+f"(d[45]),"+f"(d[46]),"+f"(d[47])
    : "l"(da), "l"(db), "r"(acc));
}
DEVINL void wgmma_ss_n64t(float (&d)[32], uint64_t da, uint64_t db, int acc) {
  asm volatile("{\n.reg .pred p;\nsetp.ne.b32 p, %34, 0;\n"
    "wgmma.mma_async.sync.aligned.m64n64k16.f32.bf16.bf16 {%0,%1,%2,%3,%4,%5,%6,%7,%8,%9,%10,%11,%12,%13,%14,%15,%16,%17,%18,%19,%20,%21,%22,%23,%24,%25,%26,%27,%28,%29,%30,%31}, %32, %33, p, 1, 1, 0, 1;\n}\n"
    : "+f"(d[0]),"+f"(d[1]),"+f"(d[2]),"+f"(d[3]),"+f"(d[4]),"+f"(d[5]),"+f"(d[6]),"+f"(d[7]),"+f"(d[8]),"+f"(d[9]),"+f"(d[10]),"+f"(d[11]),"+f"(d[12]),"+f"(d[13]),"+f"(d[14]),"+f"(d[15]),"+f"(d[16]),"+f"(d[17]),"+f"(d[18]),"+f"(d[19]),"+f"(d[20]),"+f"(d[21]),"+f"(d[22]),"+f"(d[23]),"+f"(d[24]),"+f"(d[25]),"+f"(d[26]),"+f"(d[27]),"+f"(d[28]),"+f"(d[29]),"+f"(d[30]),"+f"(d[31])
    : "l"(da), "l"(db), "r"(acc));
}
DEVINL void wgmma_ss_n160t(float (&d)[80], uint64_t da, uint64_t db, int acc) {
  asm volatile("{\n.reg .pred p;\nsetp.ne.b32 p, %82, 0;\n"
    "wgmma.mma_async.sync.aligned.m64n160k16.f32.bf16.bf16 {%0,%1,%2,%3,%4,%5,%6,%7,%8,%9,%10,%11,%12,%13,%14,%15,%16,%17,%18,%19,%20,%21,%22,%23,%24,%25,%26,%27,%28,%29,%30,%31,%32,%33,%34,%35,%36,%37,%38,%39,%40,%41,%42,%43,%44,%45,%46,%47,%48,%49,%50,%51,%52,%53,%54,%55,%56,%57,%58,%59,%60,%61,%62,%63,%64,%65,%66,%67,%68,%69,%70,%71,%72,%73,%74,%75,%76,%77,%78,%79}, %80, %81, p, 1, 1, 0, 1;\n}\n"
    : "+f"(d[0]),"+f"(d[1]),"+f"(d[2]),"+f"(d[3]),"+f"(d[4]),"+f"(d[5]),"+f"(d[6]),"+f"(d[7]),"+f"(d[8]),"+f"(d[9]),"+f"(d[10]),"+f"(d[11]),"+f"(d[12]),"+f"(d[13]),"+f"(d[14]),"+f"(d[15]),"+f"(d[16]),"+f"(d[17]),"+f"(d[18]),"+f"(d[19]),"+f"(d[20]),"+f"(d[21]),"+f"(d[22]),"+f"(d[23]),"+f"(d[24]),"+f"(d[25]),"+f"(d[26]),"+f"(d[27]),"+f"(d[28]),"+f"(d[29]),"+f"(d[30]),"+f"(d[31]),"+f"(d[32]),"+f"(d[33]),"+f"(d[34]),"+f"(d[35]),"+f"(d[36]),"+f"(d[37]),"+f"(d[38]),"+f"(d[39]),"+f"(d[40]),"+f"(d[41]),"+f"(d[42]),"+f"(d[43]),"+f"(d[44]),"+f"(d[45]),"+f"(d[46]),"+f"(d[47]),"+f"(d[48]),"+f"(d[49]),"+f"(d[50]),"+f"(d[51]),"+f"(d[52]),"+f"(d[53]),"+f"(d[54]),"+f"(d[55]),"+f"(d[56]),"+f"(d[57]),"+f"(d[58]),"+f"(d[59]),"+f"(d[60]),"+f"(d[61]),"+f"(d[62]),"+f"(d[63]),"+f"(d[64]),"+f"(d[65]),"+f"(d[66]),"+f"(d[67]),"+f"(d[68]),"+f"(d[69]),"+f"(d[70]),"+f"(d[71]),"+f"(d[72]),"+f"(d[73]),"+f"(d[74]),"+f"(d[75]),"+f"(d[76]),"+f"(d[77]),"+f"(d[78]),"+f"(d[79])
    : "l"(da), "l"(db), "r"(acc));
}
DEVINL void wgmma_rs_n64t(float (&d)[32], uint32_t a0, uint32_t a1, uint32_t a2, uint32_t a3, uint64_t db, int acc) {
  asm volatile("{\n.reg .pred p;\nsetp.ne.b32 p, %37, 0;\n"
    "wgmma.mma_async.sync.aligned.m64n64k16.f32.bf16.bf16 {%0,%1,%2,%3,%4,%5,%6,%7,%8,%9,%10,%11,%12,%13,%14,%15,%16,%17,%18,%19,%20,%21,%22,%23,%24,%25,%26,%27,%28,%29,%30,%31}, {%32,%33,%34,%35}, %36, p, 1, 1, 1;\n}\n"
    : "+f"(d[0]),"+f"(d[1]),"+f"(d[2]),"+f"(d[3]),"+f"(d[4]),"+f"(d[5]),"+f"(d[6]),"+f"(d[7]),"+f"(d[8]),"+f"(d[9]),"+f"(d[10]),"+f"(d[11]),"+f"(d[12]),"+f"(d[13]),"+f"(d[14]),"+f"(d[15]),"+f"(d[16]),"+f"(d[17]),"+f"(d[18]),"+f"(d[19]),"+f"(d[20]),"+f"(d[21]),"+f"(d[22]),"+f"(d[23]),"+f"(d[24]),"+f"(d[25]),"+f"(d[26]),"+f"(d[27]),"+f"(d[28]),"+f"(d[29]),"+f"(d[30]),"+f"(d[31])
    : "r"(a0), "r"(a1), "r"(a2), "r"(a3), "l"(db), "r"(acc));
}
DEVINL void wgmma_rs_n128t(float (&d)[64], uint32_t a0, uint32_t a1, uint32_t a2, uint32_t a3, uint64_t db, int acc) {
  asm volatile("{\n.reg .pred p;\nsetp.ne.b32 p, %69, 0;\n"
    "wgmma.mma_async.sync.aligned.m64n128k16.f32.bf16.bf16 {%0,%1,%2,%3,%4,%5,%6,%7,%8,%9,%10,%11,%12,%13,%14,%15,%16,%17,%18,%19,%20,%21,%22,%23,%24,%25,%26,%27,%28,%29,%30,%31,%32,%33,%34,%35,%36,%37,%38,%39,%40,%41,%42,%43,%44,%45,%46,%47,%48,%49,%50,%51,%52,%53,%54,%55,%56,%57,%58,%59,%60,%61,%62,%63}, {%64,%65,%66,%67}, %68, p, 1, 1, 1;\n}\n"
    : "+f"(d[0]),"+f"(d[1]),"+f"(d[2]),"+f"(d[3]),"+f"(d[4]),"+f"(d[5]),"+f"(d[6]),"+f"(d[7]),"+f"(d[8]),"+f"(d[9]),"+f"(d[10]),"+f"(d[11]),"+f"(d[12]),"+f"(d[13]),"+f"(d[14]),"+f"(d[15]),"+f"(d[16]),"+f"(d[17]),"+f"(d[18]),"+f"(d[19]),"+f"(d[20]),"+f"(d[21]),"+f"(d[22]),"+f"(d[23]),"+f"(d[24]),"+f"(d[25]),"+f"(d[26]),"+f"(d[27]),"+f"(d[28]),"+f"(d[29]),"+f"(d[30]),"+f"(d[31]),"+f"(d[32]),"+f"(d[33]),"+f"(d[34]),"+f"(d[35]),"+f"(d[36]),"+f"(d[37]),"+f"(d[38]),"+f"(d[39]),"+f"(d[40]),"+f"(d[41]),"+f"(d[42]),"+f"(d[43]),"+f"(d[44]),"+f"(d[45]),"+f"(d[46]),"+f"(d[47]),"+f"(d[48]),"+f"(d[49]),"+f"(d[50]),"+f"(d[51]),"+f"(d[52]),"+f"(d[53]),"+f"(d[54]),"+f"(d[55]),"+f"(d[56]),"+f"(d[57]),"+f"(d[58]),"+f"(d[59]),"+f"(d[60]),"+f"(d[61]),"+f"(d[62]),"+f"(d[63])
    : "r"(a0), "r"(a1), "r"(a2), "r"(a3), "l"(db), "r"(acc));
}
DEVINL void wgmma_ss_n128t(float (&d)[64], uint64_t da, uint64_t db, int acc) {
  asm volatile("{\n.reg .pred p;\nsetp.ne.b32 p, %66, 0;\n"
    "wgmma.mma_async.sync.aligned.m64n128k16.f32.bf16.bf16 {%0,%1,%2,%3,%4,%5,%6,%7,%8,%9,%10,%11,%12,%13,%14,%15,%16,%17,%18,%19,%20,%21,%22,%23,%24,%25,%26,%27,%28,%29,%30,%31,%32,%33,%34,%35,%36,%37,%38,%39,%40,%41,%42,%43,%44,%45,%46,%47,%48,%49,%50,%51,%52,%53,%54,%55,%56,%57,%58,%59,%60,%61,%62,%63}, %64, %65, p, 1, 1, 0, 1;\n}\n"
    : "+f"(d[0]),"+f"(d[1]),"+f"(d[2]),"+f"(d[3]),"+f"(d[4]),"+f"(d[5]),"+f"(d[6]),"+f"(d[7]),"+f"(d[8]),"+f"(d[9]),"+f"(d[10]),"+f"(d[11]),"+f"(d[12]),"+f"(d[13]),"+f"(d[14]),"+f"(d[15]),"+f"(d[16]),"+f"(d[17]),"+f"(d[18]),"+f"(d[19]),"+f"(d[20]),"+f"(d[21]),"+f"(d[22]),"+f"(d[23]),"+f"(d[24]),"+f"(d[25]),"+f"(d[26]),"+f"(d[27]),"+f"(d[28]),"+f"(d[29]),"+f"(d[30]),"+f"(d[31]),"+f"(d[32]),"+f"(d[33]),"+f"(d[34]),"+f"(d[35]),"+f"(d[36]),"+f"(d[37]),"+f"(d[38]),"+f"(d[39]),"+f"(d[40]),"+f"(d[41]),"+f"(d[42]),"+f"(d[43]),"+f"(d[44]),"+f"(d[45]),"+f"(d[46]),"+f"(d[47]),"+f"(d[48]),"+f"(d[49]),"+f"(d[50]),"+f"(d[51]),"+f"(d[52]),"+f"(d[53]),"+f"(d[54]),"+f"(d[55]),"+f"(d[56]),"+f"(d[57]),"+f"(d[58]),"+f"(d[59]),"+f"(d[60]),"+f"(d[61]),"+f"(d[62]),"+f"(d[63])
    : "l"(da), "l"(db), "r"(acc));
}

constexpr uint32_t MUFU_MASK = 0x4911;
constexpr uint32_t BF_ONE = 0x3F80, BF_65536 = 0x4780, BF_127 = 0x42FE;
constexpr uint32_t OFF_A = 0x3F05, OFF_E = 0x3F8F;
constexpr float QSCALE = 0.23570226039551584f * 1.4426950408889634f;

constexpr int K1_ST = 5, K1_STB = 14336, K1_A = 147456;
constexpr int K1_SMEM = K1_A + K1_ST * K1_STB + 1024;
__global__ void __launch_bounds__(384, 1) qkv_kernel(const __grid_constant__ CUtensorMap tmW, const bf16* __restrict__ x, const bf16* __restrict__ wqkv) {
  extern __shared__ unsigned char smem_raw[];
  __shared__ uint64_t bars[2 * K1_ST];
  __shared__ int2 tab[64];
  __shared__ int npiece;
  const uint32_t sb = __shfl_sync(~0u, (smem_u32(smem_raw) + 1023) & ~1023u, 0), bb = __shfl_sync(~0u, smem_u32(bars), 0);
  const int tid = threadIdx.x, warp = __shfl_sync(~0u, tid >> 5, 0), lane = tid & 31;
  const int ct = blockIdx.x & 7, rb = blockIdx.x >> 3;
  if (tid == 0) TSTAMP(0, 0);
  uint4 v[3][9];
  const int sub = lane >> 3, j8 = lane & 7;
#pragma unroll
  for (int p = 0; p < 3; p++) {
    const int r = p * 48 + warp * 4 + sub;
    if (r < 128) {
      const uint4* src = (const uint4*)(x + (size_t)(rb * 128 + r) * D_) + j8;
#pragma unroll
      for (int c = 0; c < 9; c++) v[p][c] = __ldg(src + c * 8);
    }
  }
  if (tid == 256) {
    for (int i = 0; i < K1_ST; i++) { mbar_init(bb + 8 * i, 1); mbar_init(bb + 8 * (K1_ST + i), 2); }
    mbar_init_fence();
    for (int i = 0; i < K1_ST; i++) { mbar_expect(bb + 8 * i, K1_STB); tma3d(sb + K1_A + i * K1_STB, &tmW, 0, i * 32, ct * 7, bb + 8 * i); }
  }
  if (tid == 288) l2_prefetch((const char*)wqkv + blockIdx.x * 15552, 15552);
#pragma unroll
  for (int p = 0; p < 3; p++) {
    const int r = p * 48 + warp * 4 + sub;
    if (p * 48 + warp * 4 < 128) {
      float s = 0.f;
#pragma unroll
      for (int c = 0; c < 9; c++) {
        const uint32_t* w = (const uint32_t*)&v[p][c];
#pragma unroll
        for (int e = 0; e < 4; e++) s += bf_lo(w[e]) + bf_hi(w[e]);
      }
      s += __shfl_xor_sync(~0u, s, 1); s += __shfl_xor_sync(~0u, s, 2); s += __shfl_xor_sync(~0u, s, 4);
      const float mean = s * (1.f / D_);
      float q = 0.f;
#pragma unroll
      for (int c = 0; c < 9; c++) {
        const uint32_t* w = (const uint32_t*)&v[p][c];
#pragma unroll
        for (int e = 0; e < 4; e++) { float a = bf_lo(w[e]) - mean, b = bf_hi(w[e]) - mean; q = fmaf(a, a, q); q = fmaf(b, b, q); }
      }
      q += __shfl_xor_sync(~0u, q, 1); q += __shfl_xor_sync(~0u, q, 2); q += __shfl_xor_sync(~0u, q, 4);
      const float rstd = rsqrtf(q * (1.f / D_) + LN_EPS), nm = -mean * rstd;
      const uint32_t dst = sb + r * 128 + ((j8 ^ (r & 7)) << 4);
#pragma unroll
      for (int c = 0; c < 9; c++) {
        const uint32_t* w = (const uint32_t*)&v[p][c];
        uint32_t o[4];
#pragma unroll
        for (int e = 0; e < 4; e++) o[e] = packbf(fmaf(bf_lo(w[e]), rstd, nm), fmaf(bf_hi(w[e]), rstd, nm));
        asm volatile("st.shared.v4.b32 [%0], {%1,%2,%3,%4};" ::"r"(dst + c * 16384), "r"(o[0]), "r"(o[1]), "r"(o[2]), "r"(o[3]) : "memory");
      }
    }
  }
  FENCE_ASYNC();
  __syncthreads();
  PDL_LAUNCH();
  if (warp >= 8) {
    if (tid == 256) {
      for (int i = K1_ST; i < 18; i++) {
        const int s = i % K1_ST;
        mbar_wait(bb + 8 * (K1_ST + s), ((i / K1_ST) - 1) & 1);
        mbar_expect(bb + 8 * s, K1_STB);
        tma3d(sb + K1_A + s * K1_STB, &tmW, 0, i * 32, ct * 7, bb + 8 * s);
      }
    } else if (warp > 8) {
      if (tid == 288) {
        const int np = ct == 7 ? 80 : 112;
        int n = 0;
        for (int p = 0; p < np;) {
          const int col = ct * 224 + p * 2, sec = col / D_, c = col - sec * D_, head = c / 18, sl = c - head * 18 + (sec == 2 ? 22 : 0);
          const int pitch = sec == 0 ? 512 : 640, wide = (sl & 7) == 0 && sl != 16 && p + 4 <= np;
          tab[n++] = make_int2((sec ? NH * 256 * 512 : 0) + head * 256 * pitch + (sl >> 3) * 128 + (sl & 7) * 2, pitch | (p << 16) | (wide << 24));
          p += wide ? 4 : 1;
        }
        npiece = n;
      }
      __syncwarp();
      for (int i = tid - 288; i < 512; i += 96) {
        const int rg = rb * 16 + ((i >> 3) & 15), hr = (ct * 4 + (i >> 7)) * 256 + rg;
        unsigned char* q = g_qimg + (size_t)hr * 512 + 256 + (i & 7) * 16;
        *(uint32_t*)(q + 4) = BF_65536 << 16; *(uint2*)(q + 8) = make_uint2(BF_ONE | (OFF_A << 16), 0);
        *(uint4*)(q + 128) = make_uint4(0, 0, 0, 0);
        unsigned char* k = g_kvimg + (size_t)hr * 640 + 256 + (i & 7) * 16;
        const bool mufu = (MUFU_MASK >> (rg & 15)) & 1;
        *(uint32_t*)(k + 4) = BF_ONE | (mufu ? 0u : (BF_ONE << 16));
        *(uint32_t*)(k + 8) = mufu ? (OFF_E << 16) : BF_127;
      }
    }
  } else {
  if (tid == 0) TSTAMP(0, 1);
  const int wg = warp >> 2;
  float acc[112];
  def_f(acc);
  const uint64_t dA = mkdesc(sb + wg * 8192, 16, 1024, 1), dB = mkdesc(sb + K1_A, 2048, 512, 2);
#pragma unroll
  for (int i = 0; i < 18; i++) {
    const int s = i % K1_ST;
    mbar_wait(bb + 8 * s, (i / K1_ST) & 1);
    WG_FENCE();
    const uint64_t a = dA + (i >> 1) * 1024 + (i & 1) * 4, b = dB + s * (K1_STB / 16);
    wgmma_ss_n224t(acc, a, b, i);
    wgmma_ss_n224t(acc, a + 2, b + 64, 1);
    WG_COMMIT();
    WG_WAIT(1);
    if (i > 0 && (tid & 127) == 0) mbar_arrive(bb + 8 * (K1_ST + (i - 1) % K1_ST));
  }
  WG_WAIT(0);
  pin_f(acc);
  if (tid == 0) TSTAMP(0, 2);
  const uint32_t st = sb + (warp & 3) * 16384 + wg * 8192 + (lane & 15) * 464 + (lane >> 4) * 16;
  named_sync(1 + wg, 128);
#pragma unroll
  for (int i = 0; i < 28; i += 2) {
    const float s0 = ct * 224 + i * 8 < D_ ? QSCALE : 1.f;
    stsm4(st + i * 16, packbf(acc[4 * i] * s0, acc[4 * i + 1] * s0), packbf(acc[4 * i + 2] * s0, acc[4 * i + 3] * s0),
          packbf(acc[4 * i + 4] * s0, acc[4 * i + 5] * s0), packbf(acc[4 * i + 6] * s0, acc[4 * i + 7] * s0));
  }
  }
  __syncthreads();
  {
    const int row = tid & 127, n = npiece;
    const uint32_t src = sb + ((row >> 4) & 3) * 16384 + (row >> 6) * 8192 + (row & 15) * 464;
    unsigned char* dst = g_img + (row & 7) * 16;
    const int rg = rb * 16 + (row >> 3);
#pragma unroll 4
    for (int j = tid >> 7; j < n; j += 3) {
      const int2 e = tab[j];
      const uint32_t a = src + ((e.y >> 16) & 255) * 4;
      unsigned char* p = dst + (e.x + rg * (e.y & 0xFFFF));
      uint4 v;
      asm volatile("ld.shared.b32 %0, [%1];" : "=r"(v.x) : "r"(a));
      if (e.y >> 24) {
        asm volatile("ld.shared.b32 %0, [%1+4];" : "=r"(v.y) : "r"(a));
        asm volatile("ld.shared.b32 %0, [%1+8];" : "=r"(v.z) : "r"(a));
        asm volatile("ld.shared.b32 %0, [%1+12];" : "=r"(v.w) : "r"(a));
        *(uint4*)p = v;
      } else *(uint32_t*)p = v.x;
    }
  }
  if (tid == 0) TSTAMP(0, 3);
}

constexpr int HEADB = 256 * 640;
constexpr int K2_SMEM = HEADB + 32768 + 128;

DEVINL uint32_t exp2_bits(float t0, float t1, uint32_t half2) {
  const uint32_t w = __byte_perm(__float_as_uint(t0), __float_as_uint(t1), 0x5410);
  const uint32_t e = w & 0xFF80FF80u;
  uint32_t m, r;
  asm("lop3.b32 %0,%1,0x007F007F,%2,0xEA;" : "=r"(m) : "r"(w), "r"(half2));
  asm("fma.rn.bf16x2 %0,%1,%2,%3;" : "=r"(r) : "r"(w), "r"(m), "r"(e));
  return r;
}
DEVINL void attn_store(const float (&o)[12], int row, int head, int lane) {
  const int t = lane & 3;
  const float l0 = __shfl_sync(~0u, o[0], (lane & ~3) | 1), l1 = __shfl_sync(~0u, o[2], (lane & ~3) | 1);
  const float r0 = __frcp_rn(l0), r1 = __frcp_rn(l1);
  bf16* op = g_O + (size_t)row * D_ + head * 18;
  if (t == 3) { *(uint32_t*)(op) = packbf(o[0] * r0, o[1] * r0); *(uint32_t*)(op + 8 * D_) = packbf(o[2] * r1, o[3] * r1); }
  *(uint32_t*)(op + 2 + 2 * t) = packbf(o[4] * r0, o[5] * r0);   *(uint32_t*)(op + 8 * D_ + 2 + 2 * t) = packbf(o[6] * r1, o[7] * r1);
  *(uint32_t*)(op + 10 + 2 * t) = packbf(o[8] * r0, o[9] * r0);  *(uint32_t*)(op + 8 * D_ + 10 + 2 * t) = packbf(o[10] * r1, o[11] * r1);
}
DEVINL float sq8(uint4 v) {
  float s = 0.f;
  const uint32_t w[4] = {v.x, v.y, v.z, v.w};
#pragma unroll
  for (int e = 0; e < 4; e++) { float a = bf_lo(w[e]), b = bf_hi(w[e]); s = fmaf(a, a, s); s = fmaf(b, b, s); }
  return s;
}

__global__ void __launch_bounds__(512, 1) attn_kernel(const bf16* __restrict__ wo, const bf16* __restrict__ w1, const bf16* __restrict__ w2,
                                                      const bf16* __restrict__ w3, const bf16* __restrict__ w4) {
  extern __shared__ unsigned char smem_raw[];
  __shared__ uint64_t bars[18];
  __shared__ float red[32];
  unsigned char* smem = smem_raw + ((128 - (smem_u32(smem_raw) & 127)) & 127);
  const uint32_t sb = smem_u32(smem), bb = smem_u32(bars);
  const int head = blockIdx.x >> 2, qc = blockIdx.x & 3;
  const int tid = threadIdx.x, lane = tid & 31;
  const int wg = __shfl_sync(~0u, tid >> 7, 0);
  if (tid == 0) TSTAMP(1, 0);
  if (tid == 0) {
    for (int i = 0; i < 18; i++) mbar_init(bb + 8 * i, 1);
    mbar_init_fence();
  }
  if (tid == 32) {
    l2_prefetch((const char*)wo + blockIdx.x * 5184, 5184); l2_prefetch((const char*)w1 + blockIdx.x * 5184, 5184);
    l2_prefetch((const char*)w2 + blockIdx.x * 5184, 5184);
    l2_prefetch((const char*)w3 + blockIdx.x * 41472, 41472); l2_prefetch((const char*)w4 + blockIdx.x * 41472, 41472);
  }
  __syncthreads();
  PDL_WAIT();
  if (tid == 0) TSTAMP(1, 1);
  if (tid == 0) {
    const unsigned char* qsrc = g_qimg + (size_t)(head * 256 + qc * 64) * 512;
    const unsigned char* ksrc = g_kvimg + (size_t)head * HEADB;
    mbar_expect(bb, 10240); bulk_g2s(sb, ksrc, 10240, bb);
    mbar_expect(bb + 128, 16384); bulk_g2s(sb + HEADB, qsrc, 16384, bb + 128);
    for (int c = 1; c < 16; c++) { mbar_expect(bb + 8 * c, 10240); bulk_g2s(sb + c * 10240, ksrc + c * 10240, 10240, bb + 8 * c); }
    mbar_expect(bb + 136, 16384); bulk_g2s(sb + HEADB + 16384, qsrc + 16384, 16384, bb + 136);
  }
  __syncwarp();
  uint32_t half2 = 0x3F003F00u;
  asm volatile("" : "+r"(half2));
  const uint64_t dK = mkdesc(sb, 128, 640, 0), dV = mkdesc(sb + 256, 640, 128, 0);
  uint64_t dQ = mkdesc(sb + HEADB + wg * 4096, 128, 512, 0);
  const int row_base = qc * 512 + (tid >> 5) * 16 + (lane >> 2);
  {
    float o[12];
    def_f(o);
    mbar_wait(bb + 128, 0);
    if (tid == 0) TSTAMP(1, 2);
#pragma unroll 1
    for (int jj = 0; jj < 32; jj++) {
      const int j = jj & 15;
      const uint32_t off = j * 640;
      float s[64]; uint32_t p[32];
      def_f(s);
      if (jj <= 16) { mbar_wait(bb + (jj < 16 ? 8 * jj : 136), 0); if (jj == 16) dQ += 1024; }
      WG_FENCE();
      wgmma_ss_n128(s, dQ, dK + off, 0);
      wgmma_ss_n128(s, dQ + 16, dK + off + 16, 1);
      WG_COMMIT();
      WG_WAIT(0);
      pin_f(s);
#pragma unroll
      for (int hf = 0; hf < 2; hf++) {
#pragma unroll
        for (int i = hf * 8; i < hf * 8 + 8; i++) {
          if ((MUFU_MASK >> i) & 1) {
            p[2 * i] = packbf(ex2f(s[4 * i]), ex2f(s[4 * i + 1]));
            p[2 * i + 1] = packbf(ex2f(s[4 * i + 2]), ex2f(s[4 * i + 3]));
          } else {
            p[2 * i] = exp2_bits(s[4 * i], s[4 * i + 1], half2);
            p[2 * i + 1] = exp2_bits(s[4 * i + 2], s[4 * i + 3], half2);
          }
        }
#pragma unroll
        for (int i = hf * 16; i < hf * 16 + 16; i++) asm volatile("" : "+r"(p[i])::"memory");
        WG_FENCE();
#pragma unroll
        for (int kk = hf * 4; kk < hf * 4 + 4; kk++)
          wgmma_rs_n24t(o, p[4 * kk], p[4 * kk + 1], p[4 * kk + 2], p[4 * kk + 3], dV + off + kk * 80, kk == 0 ? j : 1);
      }
      WG_COMMIT();
      WG_WAIT(0);
      pin_f(o); pin_r(p);
      if (j == 15) attn_store(o, row_base + (jj >> 4) * 256, head, lane);
    }
  }
  if (tid == 0) TSTAMP(1, 3);
  PDL_LAUNCH();
  float kmax = 0.f;
#pragma unroll
  for (int i = 0; i < 4; i++) {
    const int key = tid + i * 512;
    const unsigned char* kp = smem + (key >> 3) * 640 + (key & 7) * 16;
    const uint32_t w = *(const uint32_t*)(kp + 256);
    float n = sq8(*(const uint4*)kp) + sq8(*(const uint4*)(kp + 128));
    n = fmaf(bf_lo(w), bf_lo(w), fmaf(bf_hi(w), bf_hi(w), n));
    kmax = (n > kmax || n != n) ? n : kmax;
  }
  float qmax;
  {
    const unsigned char* qp = smem + HEADB + (tid >> 3) * 512 + (tid & 7) * 16;
    const uint32_t w = *(const uint32_t*)(qp + 256);
    qmax = sq8(*(const uint4*)qp) + sq8(*(const uint4*)(qp + 128));
    qmax = fmaf(bf_lo(w), bf_lo(w), fmaf(bf_hi(w), bf_hi(w), qmax));
  }
  const uint32_t km = __reduce_max_sync(~0u, __float_as_uint(kmax) & 0x7FFFFFFFu), qm = __reduce_max_sync(~0u, __float_as_uint(qmax) & 0x7FFFFFFFu);
  if (lane == 0) { red[tid >> 5] = __uint_as_float(km); red[16 + (tid >> 5)] = __uint_as_float(qm); }
  __syncthreads();
  const uint32_t km2 = __reduce_max_sync(~0u, __float_as_uint(red[lane & 15])), qm2 = __reduce_max_sync(~0u, __float_as_uint(red[16 + (lane & 15)]));
  if (tid == 0) TSTAMP(1, 4);
  if (__uint_as_float(km2) * __uint_as_float(qm2) <= 3600.f) return;

  *(uint32_t*)(smem + HEADB + (tid >> 3) * 512 + (tid & 7) * 16 + 256 + 4) = 0;
  *(uint32_t*)(smem + HEADB + (tid >> 3) * 512 + (tid & 7) * 16 + 256 + 8) = 0;
  FENCE_ASYNC();
  __syncthreads();
  dQ -= 1024;
#pragma unroll 1
  for (int round = 0; round < 2; round++) {
    float o[12], m0 = -INFINITY, m1 = -INFINITY;
#pragma unroll
    for (int i = 0; i < 12; i++) o[i] = 0.f;
#pragma unroll 1
    for (int j = 0; j < 16; j++) {
      const uint32_t off = j * 640;
      float s[64]; uint32_t p[32];
      def_f(s);
      WG_FENCE();
      wgmma_ss_n128(s, dQ, dK + off, 0);
      wgmma_ss_n128(s, dQ + 16, dK + off + 16, 1);
      WG_COMMIT();
      WG_WAIT(0);
      pin_f(s);
      float n0 = m0, n1 = m1;
#pragma unroll
      for (int i = 0; i < 16; i++) { n0 = fmaxf(n0, fmaxf(s[4 * i], s[4 * i + 1])); n1 = fmaxf(n1, fmaxf(s[4 * i + 2], s[4 * i + 3])); }
      n0 = fmaxf(n0, __shfl_xor_sync(~0u, n0, 1)); n0 = fmaxf(n0, __shfl_xor_sync(~0u, n0, 2));
      n1 = fmaxf(n1, __shfl_xor_sync(~0u, n1, 1)); n1 = fmaxf(n1, __shfl_xor_sync(~0u, n1, 2));
      const float c0 = ex2f(m0 - n0), c1 = ex2f(m1 - n1);
      m0 = n0; m1 = n1;
#pragma unroll
      for (int i = 0; i < 3; i++) { o[4 * i] *= c0; o[4 * i + 1] *= c0; o[4 * i + 2] *= c1; o[4 * i + 3] *= c1; }
#pragma unroll
      for (int i = 0; i < 16; i++) {
        p[2 * i] = packbf(ex2f(s[4 * i] - m0), ex2f(s[4 * i + 1] - m0));
        p[2 * i + 1] = packbf(ex2f(s[4 * i + 2] - m1), ex2f(s[4 * i + 3] - m1));
      }
      pin_r(p); pin_f(o);
      WG_FENCE();
#pragma unroll
      for (int kk = 0; kk < 8; kk++) wgmma_rs_n24t(o, p[4 * kk], p[4 * kk + 1], p[4 * kk + 2], p[4 * kk + 3], dV + off + kk * 80, 1);
      WG_COMMIT();
      WG_WAIT(0);
      pin_f(o); pin_r(p);
    }
    attn_store(o, row_base + round * 256, head, lane);
    dQ += 1024;
  }
}

constexpr int K3_ST = 6, K3_STB = 24576, K3_A = 73728;
constexpr int K3_SMEM = K3_A + K3_ST * K3_STB + 1024;
DEVINL void st_async4(uint32_t dst_cl, float a, float b, float c, float d, uint32_t bar_cl) {
  asm volatile("st.async.weak.shared::cluster.mbarrier::complete_tx::bytes.v4.f32 [%0], {%1,%2,%3,%4}, [%5];"
               ::"r"(dst_cl), "f"(a), "f"(b), "f"(c), "f"(d), "r"(bar_cl) : "memory");
}
DEVINL float quad_sum(float v) { v += __shfl_xor_sync(~0u, v, 1); return v + __shfl_xor_sync(~0u, v, 2); }
DEVINL void row_stats(const float (&a)[48], float4* st, uint32_t bar, int part, int slot, int t, float& m0, float& v0, float& m1, float& v1) {
  float s0 = 0.f, s1 = 0.f;
#pragma unroll
  for (int i = 0; i < 12; i++) { s0 += a[4 * i] + a[4 * i + 1]; s1 += a[4 * i + 2] + a[4 * i + 3]; }
  s0 = quad_sum(s0) * (1.f / 96); s1 = quad_sum(s1) * (1.f / 96);
  float q0 = 0.f, q1 = 0.f;
#pragma unroll
  for (int i = 0; i < 12; i++) {
    const float a0 = a[4 * i] - s0, a1 = a[4 * i + 1] - s0, b0 = a[4 * i + 2] - s1, b1 = a[4 * i + 3] - s1;
    q0 = fmaf(a0, a0, fmaf(a1, a1, q0)); q1 = fmaf(b0, b0, fmaf(b1, b1, q1));
  }
  q0 = quad_sum(q0); q1 = quad_sum(q1);
  if (t < 3) st_async4(mapa(smem_u32(st + part * 32 + slot), t), s0, q0, s1, q1, mapa(bar, t));
  mbar_wait(bar, 0);
  float4 p[6];
  m0 = 0.f; m1 = 0.f;
#pragma unroll
  for (int i = 0; i < 6; i++) { p[i] = st[i * 32 + slot]; m0 += p[i].x; m1 += p[i].z; }
  m0 *= (1.f / 6); m1 *= (1.f / 6);
  v0 = 0.f; v1 = 0.f;
#pragma unroll
  for (int i = 0; i < 6; i++) {
    const float d0 = p[i].x - m0, d1 = p[i].z - m1;
    v0 += fmaf(96.f * d0, d0, p[i].y); v1 += fmaf(96.f * d1, d1, p[i].w);
  }
  v0 *= (1.f / D_); v1 *= (1.f / D_);
}

__global__ void __cluster_dims__(3, 1, 1) __launch_bounds__(288, 1)
mid_kernel(const __grid_constant__ CUtensorMap tmO, const __grid_constant__ CUtensorMap tmWo, const __grid_constant__ CUtensorMap tmW1,
           const __grid_constant__ CUtensorMap tmW2, const bf16* __restrict__ x, bf16* __restrict__ out) {
  extern __shared__ unsigned char smem_raw[];
  __shared__ uint64_t bars[2 * K3_ST + 30];
  __shared__ float4 stats[2][6 * 32];
  __shared__ __align__(16) unsigned char dump[16];
  const uint32_t sb = __shfl_sync(~0u, (smem_u32(smem_raw) + 1023) & ~1023u, 0), bb = __shfl_sync(~0u, smem_u32(bars), 0);
  const uint32_t bAF = bb + 16 * K3_ST, bST = bAF + 216, bD1 = bST + 16;
  const int tid = threadIdx.x, warp = __shfl_sync(~0u, tid >> 5, 0), lane = tid & 31;
  const int rank = cluster_rank(), R0 = (blockIdx.x / 3) * 60 - 2;
  if (tid == 0) TSTAMP(2, 0);
  if (tid == 256) {
    for (int i = 0; i < K3_ST; i++) { mbar_init(bb + 8 * i, 1); mbar_init(bb + 8 * (K3_ST + i), 2); }
    for (int i = 0; i < 29; i++) mbar_init(bAF + 8 * i, 1);
    mbar_init(bD1, 24);
    for (int i = 0; i < 27; i++) mbar_expect(bAF + 8 * i, 8192);
    mbar_expect(bST, 3072); mbar_expect(bST + 8, 3072);
    mbar_init_fence();
    for (int i = 0; i < K3_ST; i++) { mbar_expect(bb + 8 * i, K3_STB); tma3d(sb + K3_A + i * K3_STB, &tmWo, 0, i * 64, rank * 3, bb + 8 * i); }
  }
  cluster_sync();
  PDL_LAUNCH();
  if (warp == 8) {
    if (lane == 0) {
      PDL_WAIT();
      TSTAMP(2, 1);
      for (int c = 0; c < 3; c++) tma3d_mc(sb + (c * 3 + rank) * 8192, &tmO, 0, R0, c * 3 + rank, bAF + 8 * (c * 3 + rank), 7);
      for (int i = K3_ST; i < 27; i++) {
        const int s = i % K3_ST, gi = i / 9, j = i - gi * 9;
        const int kc = gi ? (rank * 3 + j) % 9 : j;
        mbar_wait(bb + 8 * (K3_ST + s), ((i / K3_ST) - 1) & 1);
        mbar_expect(bb + 8 * s, K3_STB);
        tma3d(sb + K3_A + s * K3_STB, gi == 0 ? &tmWo : (gi == 1 ? &tmW1 : &tmW2), 0, kc * 64, rank * 3, bb + 8 * s);
      }
    }
    return;
  }
  const int wg = warp >> 2, g = lane >> 2, t = lane & 3;
  const int lr = (warp & 3) * 16 + g, gr = R0 + lr;
  auto cblk = [&](int i) { return rank * 24 + (i < 8 ? wg * 8 + i : 8 + wg * 4 + i); };
  const bool in0 = gr >= 0 && gr < S_, in1 = gr + 8 < S_;
  float acc[48], h[48];
  uint32_t xr[24];
  const bf16 *x0 = x + (size_t)max(gr, 0) * D_ + t * 2, *x1 = x + (size_t)min(gr + 8, S_ - 1) * D_ + t * 2;
  if (gr >= S_) x0 = x1;
  {
#pragma unroll
    for (int i = 0; i < 12; i++) {
      const uint32_t a = __ldg((const uint32_t*)(x0 + cblk(i) * 8));
      const uint32_t b = __ldg((const uint32_t*)(x1 + cblk(i) * 8));
      xr[2 * i] = a; xr[2 * i + 1] = b;
    }
  }
  const uint64_t dA = mkdesc(sb, 16, 1024, 1), dB = mkdesc(sb + K3_A + wg * 8192, wg ? 8192 + 64 : 16384, 1024, 1);
  const bool lead = (tid & 127) == 0;
  auto gemm = [&](const int gi) {
    pin_f(acc);
    bool oka = false, okb = false;
#pragma unroll
    for (int j = 0; j < 9; j++) {
      const int it = gi * 9 + j, s = it % K3_ST;
      int kc = gi ? rank * 3 + j : j;
      if (kc >= 9) kc -= 9;
      if (!oka && (gi == 0 || j >= 3)) mbar_wait(bAF + 72 * gi + 8 * kc, 0);
      if (!okb) mbar_wait(bb + 8 * s, (it / K3_ST) & 1);
      WG_FENCE();
      const uint64_t a = dA + kc * 512, b = dB + s * (K3_STB / 16);
      wgmma_ss_n96t(acc, a, b, (gi == 2) | j);
      if (j < 8) oka = mbar_test(bAF + 72 * gi + 8 * (kc == 8 ? 0 : kc + 1), 0);
      if (j < 8) okb = mbar_test(bb + 8 * ((it + 1) % K3_ST), ((it + 1) / K3_ST) & 1);
      wgmma_ss_n96t(acc, a + 2, b + 128, 1);
      wgmma_ss_n96t(acc, a + 4, b + 256, 1);
      wgmma_ss_n96t(acc, a + 6, b + 384, 1);
      WG_COMMIT();
      WG_WAIT(1);
      if (j > 0 && lead) mbar_arrive(bb + 8 * (K3_ST + (it - 1) % K3_ST));
    }
    WG_WAIT(0);
    if (lead) mbar_arrive(bb + 8 * (K3_ST + (gi * 9 + 8) % K3_ST));
    pin_f(acc);
  };
  const int srow = (warp & 3) * 16 + (lane & 15), hi = lane >> 4;
  auto a_addr = [&](int row, int blk) { return sb + (blk >> 3) * 8192 + row * 128 + (((blk ^ row) & 7) << 4); };
  auto exchange = [&](int gi) {
    FENCE_ASYNC();
    named_sync(1, 256);
    if (lane == 0 && warp < 6) {
      const int c = rank * 3 + (warp < 3 ? warp : warp - 3), p = warp < 3 ? (rank == 0 ? 2 : rank - 1) : (rank == 2 ? 0 : rank + 1);
      bulk_s2s(mapa(sb + c * 8192, p), sb + c * 8192, 8192, mapa(bAF + 72 * gi + 8 * c, p));
    }
    __syncwarp();
  };
  const int part = rank * 2 + wg, slot = (warp & 3) * 8 + g;
  def_f(acc);
  gemm(0);
#pragma unroll
  for (int i = 0; i < 24; i++) { acc[2 * i] += bf_lo(xr[i]); acc[2 * i + 1] += bf_hi(xr[i]); }
  if (tid == 0) TSTAMP(2, 2);
  float m0, v0, m1, v1;
  row_stats(acc, stats[0], bST, part, slot, t, m0, v0, m1, v1);
  const float r0 = rsqrtf(v0 + LN_EPS), r1 = rsqrtf(v1 + LN_EPS);
  {
    const float z0 = r0 * rsqrtf(v0 * r0 * r0 + LN_EPS), z1 = r1 * rsqrtf(v1 * r1 * r1 + LN_EPS);
#pragma unroll
    for (int i = 0; i < 48; i++) h[i] = acc[i];
#pragma unroll
    for (int i = 0; i < 12; i += 2)
      stsm4(a_addr(srow, cblk(i) + hi), packbf((h[4 * i] - m0) * z0, (h[4 * i + 1] - m0) * z0), packbf((h[4 * i + 2] - m1) * z1, (h[4 * i + 3] - m1) * z1),
            packbf((h[4 * i + 4] - m0) * z0, (h[4 * i + 5] - m0) * z0), packbf((h[4 * i + 6] - m1) * z1, (h[4 * i + 7] - m1) * z1));
  }
  exchange(1);
  if (tid == 0) TSTAMP(2, 3);
  gemm(1);
  if (tid == 0) TSTAMP(2, 4);
  if (lane < 3) mbar_arrive_cluster(mapa(bD1, lane));
  {
    uint32_t p[24];
    const uint32_t k0 = in0 ? ~0u : 0u, k1 = in1 ? ~0u : 0u;
#pragma unroll
    for (int i = 0; i < 12; i++) {
      p[2 * i] = packbf(gelu_f(acc[4 * i]), gelu_f(acc[4 * i + 1])) & k0;
      p[2 * i + 1] = packbf(gelu_f(acc[4 * i + 2]), gelu_f(acc[4 * i + 3])) & k1;
      acc[4 * i] = (h[4 * i] - m0) * r0; acc[4 * i + 1] = (h[4 * i + 1] - m0) * r0;
      acc[4 * i + 2] = (h[4 * i + 2] - m1) * r1; acc[4 * i + 3] = (h[4 * i + 3] - m1) * r1;
    }
    mbar_wait(bD1, 0);
#pragma unroll
    for (int i = 0; i < 12; i += 2) {
      const int blk = cblk(i) + hi, grp = blk / 18;
      const int row = srow + ((grp & 1) ? -1 - (grp >> 1) : 1 + (grp >> 1));
      stsm4((unsigned)row < 64u ? a_addr(row, blk) : smem_u32(dump), p[2 * i], p[2 * i + 1], p[2 * i + 2], p[2 * i + 3]);
    }
  }
  exchange(2);
  if (tid == 0) TSTAMP(2, 5);
  gemm(2);
  if (tid == 0) TSTAMP(2, 6);
  row_stats(acc, stats[1], bST + 8, part, slot, t, m0, v0, m1, v1);
  {
    const float u0 = rsqrtf(v0 + LN_EPS), u1 = rsqrtf(v1 + LN_EPS);
    const uint32_t rs = sb + K3_A;
#pragma unroll
    for (int i = 0; i < 12; i += 2) {
      const int blk = cblk(i) + hi;
      stsm4(sb + (blk >> 3) * 8192 + srow * 128 + (((blk ^ (srow + R0)) & 7) << 4),
            packbf((acc[4 * i] - m0) * u0, (acc[4 * i + 1] - m0) * u0), packbf((acc[4 * i + 2] - m1) * u1, (acc[4 * i + 3] - m1) * u1),
            packbf((acc[4 * i + 4] - m0) * u0, (acc[4 * i + 5] - m0) * u0), packbf((acc[4 * i + 6] - m1) * u1, (acc[4 * i + 7] - m1) * u1));
      stsm4(rs + srow * 400 + (blk - rank * 24) * 16, packbf(acc[4 * i] + h[4 * i], acc[4 * i + 1] + h[4 * i + 1]),
            packbf(acc[4 * i + 2] + h[4 * i + 2], acc[4 * i + 3] + h[4 * i + 3]), packbf(acc[4 * i + 4] + h[4 * i + 4], acc[4 * i + 5] + h[4 * i + 5]),
            packbf(acc[4 * i + 6] + h[4 * i + 6], acc[4 * i + 7] + h[4 * i + 7]));
    }
    FENCE_ASYNC();
    named_sync(1, 256);
    const int ra = R0 + 2, re = min(R0 + 62, S_), rm = min(re, (ra | 127) + 1);
    if (lane == 8 && warp < 6) {
      const int c = rank * 3 + (warp >> 1), r0 = (warp & 1) ? rm : ra, r1 = (warp & 1) ? re : rm;
      if (r1 > r0) bulk_s2g(g_Uimg + (r0 >> 7) * 147456 + c * 16384 + (r0 & 127) * 128, sb + c * 8192 + (r0 - R0) * 128, (r1 - r0) * 128);
    } else if (lane < 8 && ra + warp * 8 + lane < re) {
      bulk_s2g(out + (size_t)(ra + warp * 8 + lane) * D_ + rank * 192, rs + (warp * 8 + lane + 2) * 400, 384);
    }
    bulk_commit();
    bulk_wait_read0();
  }
  if (tid == 0) TSTAMP(2, 7);
}

constexpr int K4_THREADS = 320, K4_ST = 4, K4_STB = 16384, K4_A = 147456;
constexpr int K4_SMEM = K4_A + K4_ST * K4_STB + 16384 + 1024;
DEVINL void stsm2(uint32_t addr, uint32_t r0, uint32_t r1) {
  asm volatile("stmatrix.sync.aligned.m8n8.x2.shared.b16 [%0], {%1,%2};" ::"r"(addr), "r"(r0), "r"(r1) : "memory");
}
__global__ void __launch_bounds__(K4_THREADS, 1) up_kernel(const __grid_constant__ CUtensorMap tmA, const __grid_constant__ CUtensorMap tmB) {
  extern __shared__ unsigned char smem_raw[];
  __shared__ uint64_t bars[2 * K4_ST + 13];
  const uint32_t sb = __shfl_sync(~0u, (smem_u32(smem_raw) + 1023) & ~1023u, 0), bb = __shfl_sync(~0u, smem_u32(bars), 0), bU = bb + 16 * K4_ST;
  const uint32_t bR = bU + 72, stg = sb + K4_A + K4_ST * K4_STB;
  const int tid = threadIdx.x, warp = __shfl_sync(~0u, tid >> 5, 0), lane = tid & 31;
  const int fs = blockIdx.x & 7, rb = blockIdx.x >> 3;
  if (tid == 0) TSTAMP(3, 0);
  if (tid == 256) {
    for (int i = 0; i < K4_ST; i++) { mbar_init(bb + 8 * i, 1); mbar_init(bb + 8 * (K4_ST + i), 2); }
    for (int i = 0; i < 9; i++) { mbar_init(bU + 8 * i, 1); mbar_expect(bU + 8 * i, 16384); }
    mbar_init(bR, 8); mbar_init(bR + 8, 8); mbar_init(bR + 16, 1); mbar_init(bR + 24, 1);
    mbar_init_fence();
    for (int i = 0; i < K4_ST; i++) { mbar_expect(bb + 8 * i, K4_STB / 2); tma3d(sb + K4_A + i * K4_STB, &tmB, 0, i * 64, fs * 9, bb + 8 * i); }
  }
  __syncthreads();
  PDL_LAUNCH();
  if (warp == 9) {
    if (lane == 0) {
      unsigned char* hdst = g_Himg + (size_t)(rb * 72 + fs * 9) * 16384;
      for (int i = 0; i < 18; i++) {
        mbar_wait(bR + 8 * (i & 1), (i >> 1) & 1);
        FENCE_ASYNC();
        bulk_s2g(hdst + i * 8192, stg + (i & 1) * 8192, 8192);
        bulk_commit();
        bulk_wait_read0();
        mbar_arrive(bR + 16 + 8 * (i & 1));
      }
      bulk_wait_read0();
    }
    return;
  }
  if (warp == 8) {
    if (lane == 0) {
      PDL_WAIT();
      TSTAMP(3, 1);
      for (int c = 0; c < 9; c++) bulk_g2s(sb + c * 16384, g_Uimg + rb * 147456 + c * 16384, 16384, bU + 8 * c);
      int k = K4_ST, ch = fs * 9;
      for (int i = K4_ST; i < 45; i++) {
        const int s = i & 3;
        mbar_wait(bb + 8 * (K4_ST + s), ((i >> 2) - 1) & 1);
        mbar_expect(bb + 8 * s, i >= 9 ? K4_STB : K4_STB / 2);
        tma3d(sb + K4_A + s * K4_STB, i >= 9 ? &tmA : &tmB, 0, k * 64, ch, bb + 8 * s);
        if (++k == 9) { k = 0; ch += i == 8 ? 1 : 2; }
      }
    }
    return;
  }
  const uint64_t dB = mkdesc(sb + K4_A, 8192, 1024, 1);
  uint64_t dA;
  const uint32_t sadr = stg + (warp * 2 + ((lane >> 3) & 1)) * 512 + (lane & 7) * 16;
  uint32_t fph = 1;
  const bool lead = (tid & 127) == 0;
  int it = 0;
#define K4_EPI(P, q)                                                                                                        \
  {                                                                                                                          \
    pin4(P[4 * (q)], P[4 * (q) + 1], P[4 * (q) + 2], P[4 * (q) + 3]);                                                        \
    const uint32_t v0 = packbf(gelu_f(P[4 * (q)]), gelu_f(P[4 * (q) + 1])), v1 = packbf(gelu_f(P[4 * (q) + 2]), gelu_f(P[4 * (q) + 3])); \
    if (((q) & 3) == 0) mbar_wait(bR + 16 + ((q) & 4) * 2, fph);                                                             \
    stsm2(sadr + ((q) & 4) * 2048 + ((q) & 3) * 128, v0, v1);                                                                \
    if (((q) & 3) == 3) { __syncwarp(); if (lane == 0) mbar_arrive(bR + ((q) & 4) * 2); }                                    \
    if (((q) & 7) == 7) fph ^= 1;                                                                                            \
  }
#define K4_TILE(MMA, C, P, FIRST, DOEPI)                                                                                     \
  dA = mkdesc(__shfl_sync(~0u, sb + (warp >> 2) * 8192, 0), 16, 1024, 1);      \
  def_f(C);                                                                                                                  \
  _Pragma("unroll") for (int k = 0; k < 9; k++, it++) {                                                                      \
    const int s = it & 3;                                                                                                    \
    if (FIRST) mbar_wait(bU + 8 * k, 0);                                                                                     \
    if (!ok) mbar_wait(bb + 8 * s, (it >> 2) & 1);                                                                           \
    const uint64_t a = dA + k * 1024, b = dB + s * (K4_STB / 16);                                                            \
    WG_FENCE(); MMA(C, a, b, k); WG_COMMIT();                                                                                            \
    if (k > 0 && !(FIRST) && (k < 5 || (DOEPI))) K4_EPI(P, (2 * k + 15) & 15)                                                                       \
    WG_FENCE(); MMA(C, a + 2, b + 128, 1); WG_COMMIT();                                                                                  \
    WG_WAIT(2);                                                                                                              \
    if (lead && it > 0) mbar_arrive(bb + 8 * (K4_ST + ((it + 3) & 3)));                                                      \
    WG_FENCE(); MMA(C, a + 4, b + 256, 1); WG_COMMIT();                                                                                  \
    if (k < 8 && !(FIRST) && (k < 4 || (DOEPI))) K4_EPI(P, (2 * k) & 15)                                                                            \
    ok = mbar_test(bb + 8 * ((it + 1) & 3), ((it + 1) >> 2) & 1);                                                             \
    WG_FENCE(); MMA(C, a + 6, b + 384, 1); WG_COMMIT();                                                                                  \
  }
  auto pin4 = [](float& a, float& b, float& c, float& d) { asm volatile("" : "+f"(a), "+f"(b), "+f"(c), "+f"(d)::"memory"); };
  float ca[64], cb[64];
  bool ok = false;
  {
    float cc[32];
    K4_TILE(wgmma_ss_n64t, cc, ca, true, false)
    WG_WAIT(0);
    pin_f(cc);
#pragma unroll
    for (int i = 0; i < 32; i++) { cb[i] = cc[i]; cb[32 + i] = 0.f; }
  }
  if (tid == 0) TSTAMP(3, 2);
#pragma unroll 1
  for (int tp = 0; tp < 2; tp++) {
    K4_TILE(wgmma_ss_n128t, ca, cb, false, tp > 0)
    K4_TILE(wgmma_ss_n128t, cb, ca, false, true)
    if (tid == 0) TSTAMP(3, 3 + tp);
  }
  WG_WAIT(0);
#pragma unroll
  for (int q = 0; q < 16; q++) K4_EPI(cb, q)
  if (tid == 0) TSTAMP(3, 5);
}

constexpr int K5_ST = 4, K5_STB = 53248;
constexpr int K5_SMEM = K5_ST * K5_STB + 1024;
__global__ void __cluster_dims__(2, 1, 1) __launch_bounds__(256, 1)
down_kernel(const __grid_constant__ CUtensorMap tmA, bf16* __restrict__ out) {
  extern __shared__ unsigned char smem_raw[];
  __shared__ uint64_t bars[2 * K5_ST];
  const uint32_t sb = __shfl_sync(~0u, (smem_u32(smem_raw) + 1023) & ~1023u, 0), bb = __shfl_sync(~0u, smem_u32(bars), 0);
  const int tid = threadIdx.x, warp = __shfl_sync(~0u, tid >> 5, 0), lane = tid & 31;
  const int rank = blockIdx.x & 1, ks = (blockIdx.x >> 1) & 3, nb = (blockIdx.x >> 3) & 1, rb = (blockIdx.x >> 4) * 2 + rank;
  if (tid == 0) TSTAMP(4, 0);
  if (tid == 0) {
    for (int i = 0; i < K5_ST; i++) { mbar_init(bb + 8 * i, 1); mbar_init(bb + 8 * (K5_ST + i), 4); mbar_expect(bb + 8 * i, K5_STB); }
    mbar_init_fence();
  }
  cluster_sync();
  const unsigned char* hsrc = g_Himg + (size_t)(rb * 72 + ks * 18) * 16384;
  const int k0 = ks * 1152 + rank * 32;
  auto load_b = [&](int i) {
    tma3d_mc(sb + (i & 3) * K5_STB + 16384 + rank * 18432, &tmA, 0, k0 + i * 64, nb * 9, bb + 8 * (i & 3), 3);
  };
  if (tid == 0) for (int i = 0; i < K5_ST; i++) load_b(i);
  PDL_WAIT();
  if (tid == 0) {
    TSTAMP(4, 1); CSTAMP(4, 6);
    for (int i = 0; i < K5_ST; i++) bulk_g2s(sb + i * K5_STB, hsrc + i * 16384, 16384, bb + 8 * i);
  }
  __syncwarp();
  float a0[64], a1[80];
#define ACC(i) ((i) < 64 ? a0[(i) < 64 ? (i) : 0] : a1[(i) < 64 ? 0 : (i) - 64])
  const uint64_t dA = mkdesc(sb + (warp >> 2) * 4096, 128, 512, 0), dB = mkdesc(sb + 16384, 2048, 512, 2);
  const uint32_t erem = mapa(bb + 8 * K5_ST, tid & 1);
  def_f(a0); def_f(a1);
#pragma unroll 1
  for (int i = 0; i < 18; i++) {
    const int s = i & 3;
    mbar_wait(bb + 8 * s, (i >> 2) & 1);
    WG_FENCE();
    const uint64_t a = dA + s * (K5_STB / 16), b = dB + s * (K5_STB / 16);
#pragma unroll
    for (int kk = 0; kk < 4; kk++) {
      const uint64_t ak = a + (kk >> 1) * 512 + (kk & 1) * 16, bk = b + (kk >> 1) * 1152 + (kk & 1) * 64;
      wgmma_ss_n128t(a0, ak, bk, i | kk);
      wgmma_ss_n160t(a1, ak, bk + 512, i | kk);
    }
    WG_COMMIT();
    if (warp == 0 && i >= 2 && i < 16) mbar_wait(bb + 8 * (K5_ST + ((i + 2) & 3)), ((i - 2) >> 2) & 1);
    if (tid == 0 && i >= 2 && i < 16) {
      const int s2 = (i + 2) & 3;
      mbar_expect(bb + 8 * s2, K5_STB);
      bulk_g2s(sb + s2 * K5_STB, hsrc + (i + 2) * 16384, 16384, bb + 8 * s2);
      load_b(i + 2);
    }
    __syncwarp();
    WG_WAIT(1);
    if (i > 0 && i < 15 && (tid & 127) < 2) mbar_arrive_cluster(erem + 8 * ((i - 1) & 3));
  }
  WG_WAIT(0);
  pin_f(a0); pin_f(a1);
  if (tid == 0) { TSTAMP(4, 2); CSTAMP(4, 7); }
  named_sync(1, 256);
  const uint32_t tb = sb + (warp * 16 + (lane & 15)) * 592;
#pragma unroll
  for (int j = 0; j < 36; j += 2)
    stsm4(tb + (j + (lane >> 4)) * 16, packbf(ACC(4 * j), ACC(4 * j + 1)), packbf(ACC(4 * j + 2), ACC(4 * j + 3)),
          packbf(ACC(4 * j + 4), ACC(4 * j + 5)), packbf(ACC(4 * j + 6), ACC(4 * j + 7)));
  FENCE_ASYNC();
  __syncwarp();
  if (tid == 0) { TSTAMP(4, 3); TSTAMP(4, 4); }
  if (lane < 16) {
    const int r = warp * 16 + ((lane + 4 * ks) & 15);
    asm volatile("cp.reduce.async.bulk.global.shared::cta.bulk_group.add.noftz.bf16 [%0], [%1], 576;"
                 ::"l"(out + (size_t)(rb * 128 + r) * D_ + nb * 288), "r"(sb + r * 592) : "memory");
    bulk_commit();
    bulk_wait_read0();
  }
  if (tid == 0) TSTAMP(4, 5);
}

typedef CUresult (*EncodeFn)(CUtensorMap*, CUtensorMapDataType, cuuint32_t, void*, const cuuint64_t*, const cuuint64_t*, const cuuint32_t*,
                             const cuuint32_t*, CUtensorMapInterleave, CUtensorMapSwizzle, CUtensorMapL2promotion, CUtensorMapFloatOOBfill);
static void make_map(EncodeFn fn, CUtensorMap* m, const void* base, int cw, int rows, int ld, int brow, int bch) {
  cuuint64_t dims[3] = {(cuuint64_t)cw, (cuuint64_t)rows, (cuuint64_t)(ld / cw)};
  cuuint64_t str[2] = {(cuuint64_t)ld * 2, (cuuint64_t)cw * 2};
  cuuint32_t box[3] = {(cuuint32_t)cw, (cuuint32_t)brow, (cuuint32_t)bch}, es[3] = {1, 1, 1};
  fn(m, CU_TENSOR_MAP_DATA_TYPE_BFLOAT16, 3, (void*)base, dims, str, box, es, CU_TENSOR_MAP_INTERLEAVE_NONE,
     cw == 64 ? CU_TENSOR_MAP_SWIZZLE_128B : CU_TENSOR_MAP_SWIZZLE_64B, CU_TENSOR_MAP_L2_PROMOTION_L2_256B, CU_TENSOR_MAP_FLOAT_OOB_FILL_NONE);
}
template <typename... KA, typename... A>
static void launch(void (*k)(KA...), int grid, int block, int smem, bool pdl, A... args) {
  cudaLaunchConfig_t c = {};
  c.gridDim = dim3(grid); c.blockDim = dim3(block); c.dynamicSmemBytes = smem; c.stream = cudaStreamPerThread;
  cudaLaunchAttribute at[1];
  at[0].id = cudaLaunchAttributeProgrammaticStreamSerialization; at[0].val.programmaticStreamSerializationAllowed = 1;
  c.attrs = at; c.numAttrs = pdl ? 1 : 0;
  cudaLaunchKernelEx(&c, k, KA(args)...);
}

extern "C" void kernel_launch(void* const* d_in, const int* in_sizes, int n_in, void* d_out, int out_size) {
  const bf16 *x = (const bf16*)d_in[0], *wqkv = (const bf16*)d_in[1], *wo = (const bf16*)d_in[2];
  const bf16 *w1 = (const bf16*)d_in[4], *w2 = (const bf16*)d_in[5], *w3 = (const bf16*)d_in[6], *w4 = (const bf16*)d_in[7];
  static EncodeFn fn = nullptr;
  static void* oaddr = nullptr;
  if (!fn) {
    cudaDriverEntryPointQueryResult qr;
    cudaGetDriverEntryPoint("cuTensorMapEncodeTiled", (void**)&fn, cudaEnableDefault, &qr);
    cudaGetSymbolAddress(&oaddr, g_O);
    cudaFuncSetAttribute(qkv_kernel, cudaFuncAttributeMaxDynamicSharedMemorySize, K1_SMEM);
    cudaFuncSetAttribute(attn_kernel, cudaFuncAttributeMaxDynamicSharedMemorySize, K2_SMEM);
    cudaFuncSetAttribute(mid_kernel, cudaFuncAttributeMaxDynamicSharedMemorySize, K3_SMEM);
    cudaFuncSetAttribute(up_kernel, cudaFuncAttributeMaxDynamicSharedMemorySize, K4_SMEM);
    cudaFuncSetAttribute(down_kernel, cudaFuncAttributeMaxDynamicSharedMemorySize, K5_SMEM);
  }
  CUtensorMap mq, mO, mo, m1, m2, m3, m3b, m4;
  make_map(fn, &mq, wqkv, 32, D_, 3 * D_, 32, 7);
  make_map(fn, &mO, oaddr, 64, S_, D_, 64, 1);
  make_map(fn, &mo, wo, 64, D_, D_, 64, 3);
  make_map(fn, &m1, w1, 64, D_, D_, 64, 3);
  make_map(fn, &m2, w2, 64, D_, D_, 64, 3);
  make_map(fn, &m3, w3, 64, D_, F_, 64, 2);
  make_map(fn, &m3b, w3, 64, D_, F_, 64, 1);
  make_map(fn, &m4, w4, 32, F_, D_, 32, 9);
  launch(qkv_kernel, 128, 384, K1_SMEM, false, mq, x, wqkv);
  launch(attn_kernel, 128, 512, K2_SMEM, true, wo, w1, w2, w3, w4);
  launch(mid_kernel, 105, 288, K3_SMEM, true, mO, mo, m1, m2, x, (bf16*)d_out);
  launch(up_kernel, 128, K4_THREADS, K4_SMEM, true, m3, m3b);
  launch(down_kernel, 128, 256, K5_SMEM, true, m4, (bf16*)d_out);
}
```
